```python
import torch

def _softmax(x, axis=-1):
    return torch.softmax(x, dim=axis)
def _gelu(x):
    return torch.nn.functional.gelu(x, approximate="tanh")
def _silu(x):
    return torch.nn.functional.silu(x)
def _sigmoid(x):
    return torch.sigmoid(x)
def _layernorm(x, axis=-1, eps=1e-5):
    m = x.mean(dim=axis, keepdim=True)
    v = x.var(dim=axis, keepdim=True, unbiased=False)
    return (x - m) / torch.sqrt(v + eps)
def _scatter_add(tgt, idx, src, axis=0):
    return tgt.clone().index_add_(axis, idx, src)
def _segment_sum(src, seg, n):
    out = torch.zeros((n,) + src.shape[1:], dtype=src.dtype)
    return out.index_add_(0, seg, src)
def _pad(x, pw):
    flat = tuple(v for pair in reversed(pw) for v in pair)
    return torch.nn.functional.pad(x, flat)

kernel_name = 'parallel_sum__sliding_block_cached__mixer_channel_mlp__decode'

def setup_inputs():

    _w = (lambda a: (lambda t: t.to(torch.bfloat16) if t.is_floating_point() else t)(torch.as_tensor(a)))
    def _A_setup():
        B, Sq, D = 1, 1, 576
        Hq, Hkv, Sk, Dh = 32, 16, 16384, 128
        assert Hq % Hkv == 0, (Hq, Hkv)
        return {
            "x": _w((lambda *s: torch.randn(*s, dtype=torch.bfloat16) * 0.05)(B, Sq, D)),
            "k_cache": _w((lambda *s: torch.randn(*s, dtype=torch.bfloat16) * 3.2)(B, Hkv, Sk, Dh)),
            "v_cache": _w((lambda *s: torch.randn(*s, dtype=torch.bfloat16) * 0.4)(B, Hkv, Sk, Dh)),
            "wq": _w((lambda *s: torch.randn(*s, dtype=torch.bfloat16) * 3.2)(D, Hq * Dh) * (D ** -0.5)),
            "wo": _w((lambda *s: torch.randn(*s, dtype=torch.bfloat16) * 0.4)(Hq * Dh, D) * ((Hq * Dh) ** -0.5)),
        }
    _A_in = _A_setup()

    def _B_setup():
        B, S, D, F = 1, 1, 576, 4608
        return {
            "x": _w((lambda *s: torch.randn(*s, dtype=torch.bfloat16) * 0.05)(B, S, D)),
            "w1": _w((lambda *s: torch.randn(*s, dtype=torch.bfloat16) * 3.2)(D, F) * (D ** -0.5)),
            "b1": _w((lambda *s: torch.randn(*s, dtype=torch.bfloat16) * 1.6)(F)),
            "w2": _w((lambda *s: torch.randn(*s, dtype=torch.bfloat16) * 0.1)(F, D) * (F ** -0.5)),
            "b2": _w((lambda *s: torch.randn(*s, dtype=torch.bfloat16) * 0.1)(D)),
        }
    _B_in = _B_setup()

    return {
        "A_x": _A_in["x"],
        "A_k_cache": _A_in["k_cache"],
        "A_v_cache": _A_in["v_cache"],
        "A_wq": _A_in["wq"],
        "A_wo": _A_in["wo"],
        "B_x": _B_in["x"],
        "B_w1": _B_in["w1"],
        "B_b1": _B_in["b1"],
        "B_w2": _B_in["w2"],
        "B_b2": _B_in["b2"],
    }

def reference(A_x, A_k_cache, A_v_cache, A_wq, A_wo, B_x, B_w1, B_b1, B_w2, B_b2):
    def _A_ref(x, k_cache, v_cache, wq, wo):
        B, Sq, D = x.shape
        Hq, Dh = 32, 128
        Hkv, Sk = k_cache.shape[1], k_cache.shape[2]
        W = min(4096, max(256, Sk // 4))
        rep = Hq // Hkv
        q = (lambda x, *d: x.permute(*d))((x @ wq).reshape(B, Sq, Hq, Dh), 0, 2, 1, 3)
        k = (lambda x, n, axis: torch.repeat_interleave(x, n, dim=axis))(k_cache[:, :, Sk - W:, :], rep, axis=1)
        v = (lambda x, n, axis: torch.repeat_interleave(x, n, dim=axis))(v_cache[:, :, Sk - W:, :], rep, axis=1)
        scores = torch.einsum("bhqd,bhkd->bhqk", q, k) * (Dh ** -0.5)
        p = _softmax(scores, axis=-1)
        o = torch.einsum("bhqk,bhkd->bhqd", p, v)
        return (lambda x, *d: x.permute(*d))(o, 0, 2, 1, 3).reshape(B, Sq, Hq * Dh) @ wo

    def _B_ref(x, w1, b1, w2, b2):
        y = _layernorm(x, axis=-1)
        h = _gelu(torch.einsum("bsd,df->bsf", y, w1) + b1)
        return torch.einsum("bsf,fd->bsd", h, w2) + b2

    x = A_x
    xn = _layernorm(x, axis=-1)
    return x + _A_ref(xn, A_k_cache, A_v_cache, A_wq, A_wo) + _B_ref(xn, B_w1, B_b1, B_w2, B_b2)
```

```cpp
#include <cuda_runtime.h>
#include <cuda.h>
#include <cuda_bf16.h>
#include <stdint.h>

namespace {

constexpr int D_MODEL = 576;
constexpr int SK = 16384, WINDOW = 4096;
constexpr int QD = 4096, FF = 4608;
constexpr int NCTA = 132, NMAIN = 128, NRED = 72;
constexpr int NTHREADS = 384;
constexpr int SLICE = 36864;
constexpr int BLK = SLICE / 4;
constexpr int UNIT = 8192;

constexpr int OFF_A = 0;
constexpr int OFF_K = OFF_A + SLICE;
constexpr int OFF_B = OFF_K + 16 * UNIT;
constexpr int OFF_W1 = OFF_K + 6 * UNIT;
constexpr int OFF_WO = OFF_W1 + SLICE;
constexpr int OFF_MISC = OFF_B + 6 * UNIT;
constexpr int OFF_MERGE = OFF_MISC;
constexpr int OFF_XN = OFF_MERGE + 8192;
constexpr int OFF_Y = OFF_XN + 1152;
constexpr int OFF_PART = OFF_MERGE;
constexpr int OFF_PARTH = OFF_Y + 1152;
constexpr int OFF_COEF = OFF_PARTH + 1152;
constexpr int OFF_Q = OFF_COEF + 512;
constexpr int OFF_RED = OFF_Q + 512;
constexpr int OFF_WM = OFF_RED + 288;
constexpr int OFF_WL = OFF_WM + 64;
constexpr int OFF_PAR = OFF_WL + 64;
constexpr int OFF_BAR = OFF_PAR + 16;
constexpr int IT_Q = 0, IT_K = 4, IT_V = 20, IT_W1 = 36, IT_WO = 40, IT_W2 = 44, NITEM = 48;
constexpr int BAR_EQ = 48, BAR_EK = 49, BAR_EV = 50, BAR_H = 51, BAR_Q = 52, BAR_O = 53, BAR_Z = 54, NBAR = 55;
constexpr int OFF_T = OFF_BAR + NBAR * 8;
constexpr int SMEM_BYTES = OFF_T + 256 + 1024;
static_assert(SMEM_BYTES <= 232448, "smem");
static_assert(OFF_WO + SLICE <= OFF_B, "smem map");

constexpr int OX_WORDS = 288;
constexpr int WMIN = 4;
constexpr int WMAX = 12;
constexpr int TAU = 350;
constexpr int TAUV = 350;
constexpr int TAUW = 394;
constexpr int T0 = 500;
constexpr int W0 = 5;
constexpr int XTAU = 330;
constexpr int OPOLL = 8;
#define EVICT_FIRST 1

__device__ unsigned g_epoch;
__device__ __align__(128) unsigned g_qx[2][NMAIN * 16];
__device__ unsigned g_zcnt;
__device__ __align__(128) unsigned g_ox[NMAIN * OX_WORDS];
__device__ __align__(128) unsigned g_px[NRED * NCTA * 8];
__device__ __forceinline__ unsigned gtime32() { unsigned t; asm volatile("mov.u32 %0, %%globaltimer_lo;" : "=r"(t)); return t; }
#define STAMP(i) do {} while (0)

__device__ __forceinline__ void mbar_init(uint32_t bar, int cnt) {
    asm volatile("mbarrier.init.shared::cta.b64 [%0], %1;" ::"r"(bar), "r"(cnt) : "memory");
}
__device__ __forceinline__ void mbar_expect_tx(uint32_t bar, uint32_t bytes) {
    asm volatile("mbarrier.arrive.expect_tx.shared::cta.b64 _, [%0], %1;" ::"r"(bar), "r"(bytes) : "memory");
}
__device__ __forceinline__ void mbar_arrive(uint32_t bar) {
    asm volatile("mbarrier.arrive.shared::cta.b64 _, [%0];" ::"r"(bar) : "memory");
}
__device__ __forceinline__ void mbar_wait(uint32_t bar) {
    asm volatile("{\n .reg .pred p;\n .reg .u32 c;\n"
                 " mbarrier.try_wait.parity.shared::cta.b64 p, [%0], 0;\n @p bra.uni D_%=;\n mov.u32 c, 0;\n"
                 "L_%=:\n mbarrier.try_wait.parity.shared::cta.b64 p, [%0], 0;\n @p bra.uni D_%=;\n"
                 " add.u32 c, c, 1;\n setp.lt.u32 p, c, 262144;\n @p bra.uni L_%=;\n D_%=:\n}"
                 ::"r"(bar) : "memory");
}
__device__ __forceinline__ void mbar_wait5(uint32_t bar, uint32_t extra) {
    uint32_t ok;
    asm volatile("{\n .reg .pred p0, p1, p2, p3, p4;\n"
                 " mbarrier.try_wait.parity.shared::cta.b64 p4, [%2], 0;\n"
                 " mbarrier.try_wait.parity.shared::cta.b64 p0, [%1], 0;\n"
                 " mbarrier.try_wait.parity.shared::cta.b64 p1, [%1+8], 0;\n"
                 " mbarrier.try_wait.parity.shared::cta.b64 p2, [%1+16], 0;\n"
                 " mbarrier.try_wait.parity.shared::cta.b64 p3, [%1+24], 0;\n"
                 " and.pred p0, p0, p1;\n and.pred p2, p2, p3;\n and.pred p0, p0, p2;\n and.pred p0, p0, p4;\n selp.u32 %0, 1, 0, p0;\n}"
                 : "=r"(ok) : "r"(bar), "r"(extra) : "memory");
    if (!ok) { mbar_wait(extra); mbar_wait(bar); mbar_wait(bar + 8); mbar_wait(bar + 16); mbar_wait(bar + 24); }
}
__device__ __forceinline__ void pace_wait(uint32_t bar, unsigned due) {
    asm volatile("{\n .reg .pred p;\n .reg .u32 t;\n"
                 "L_%=:\n mbarrier.test_wait.parity.shared::cta.b64 p, [%0], 0;\n @p bra.uni D_%=;\n"
                 " mov.u32 t, %%globaltimer_lo;\n sub.u32 t, t, %1;\n setp.lt.s32 p, t, 0;\n @p bra.uni L_%=;\n D_%=:\n}"
                 ::"r"(bar), "r"(due) : "memory");
}
constexpr uint64_t STREAM_POLICY = 0x12F0000000000000ull;
__device__ __forceinline__ void tma2d(uint32_t dst, const CUtensorMap* m, int c0, int c1, uint32_t bar) {
    asm volatile("cp.async.bulk.tensor.2d.shared::cluster.global.mbarrier::complete_tx::bytes.L2::cache_hint [%0], [%1, {%3, %4}], [%2], %5;"
                 ::"r"(dst), "l"(m), "r"(bar), "r"(c0), "r"(c1), "l"(STREAM_POLICY) : "memory");
}
__device__ __forceinline__ void tma3d(uint32_t dst, const CUtensorMap* m, int c1, uint32_t bar) {
    asm volatile("cp.async.bulk.tensor.3d.shared::cluster.global.mbarrier::complete_tx::bytes.L2::cache_hint [%0], [%1, {%4, %3, %4}], [%2], %5;"
                 ::"r"(dst), "l"(m), "r"(bar), "r"(c1), "r"(0), "l"(STREAM_POLICY) : "memory");
}
__device__ __forceinline__ void bar_sync(int id, int n) { asm volatile("bar.sync %0, %1;" ::"r"(id), "r"(n) : "memory"); }
__device__ __forceinline__ void bar_arrive(int id, int n) { asm volatile("bar.arrive %0, %1;" ::"r"(id), "r"(n) : "memory"); }

__device__ __forceinline__ uint4 ld_poll4(const unsigned* p) {
    uint4 v;
    asm volatile("ld.relaxed.gpu.global.v4.u32 {%0,%1,%2,%3}, [%4];" : "=r"(v.x), "=r"(v.y), "=r"(v.z), "=r"(v.w) : "l"(p) : "memory");
    return v;
}
__device__ __forceinline__ unsigned ld_poll1(const unsigned* p) {
    unsigned v;
    asm volatile("ld.relaxed.gpu.global.u32 %0, [%1];" : "=r"(v) : "l"(p) : "memory");
    return v;
}
__device__ __forceinline__ void st_pub1(unsigned* p, unsigned v) {
    asm volatile("st.relaxed.gpu.global.u32 [%0], %1;" ::"l"(p), "r"(v) : "memory");
}
__device__ __forceinline__ void st_pub2(unsigned* p, unsigned a, unsigned b) {
    asm volatile("st.relaxed.gpu.global.v2.u32 [%0], {%1,%2};" ::"l"(p), "r"(a), "r"(b) : "memory");
}
__device__ __forceinline__ unsigned enc(float v) { unsigned u = __float_as_uint(v); return u == 0u ? 0x80000000u : u; }

__device__ __forceinline__ float bf_lo(unsigned u) { return __uint_as_float(u << 16); }
__device__ __forceinline__ float bf_hi(unsigned u) { return __uint_as_float(u & 0xffff0000u); }
__device__ __forceinline__ float bf_round(float v) { return __bfloat162float(__float2bfloat16_rn(v)); }
__device__ __forceinline__ unsigned pack_bf(float lo, float hi) {
    unsigned r; asm("cvt.rn.bf16x2.f32 %0, %1, %2;" : "=r"(r) : "f"(hi), "f"(lo)); return r;
}
__device__ __forceinline__ float lds_f(uint32_t a) { float v; asm volatile("ld.shared.f32 %0, [%1];" : "=f"(v) : "r"(a)); return v; }
__device__ __forceinline__ unsigned lds_u(uint32_t a) { unsigned v; asm volatile("ld.shared.u32 %0, [%1];" : "=r"(v) : "r"(a)); return v; }
__device__ __forceinline__ float4 lds_f4(uint32_t a) {
    float4 v; asm volatile("ld.shared.v4.f32 {%0,%1,%2,%3}, [%4];" : "=f"(v.x), "=f"(v.y), "=f"(v.z), "=f"(v.w) : "r"(a)); return v;
}
__device__ __forceinline__ uint4 lds_u4(uint32_t a) {
    uint4 v; asm volatile("ld.shared.v4.u32 {%0,%1,%2,%3}, [%4];" : "=r"(v.x), "=r"(v.y), "=r"(v.z), "=r"(v.w) : "r"(a)); return v;
}
__device__ __forceinline__ void sts_f(uint32_t a, float v) { asm volatile("st.shared.f32 [%0], %1;" ::"r"(a), "f"(v) : "memory"); }
__device__ __forceinline__ void sts_u(uint32_t a, unsigned v) { asm volatile("st.shared.u32 [%0], %1;" ::"r"(a), "r"(v) : "memory"); }
__device__ __forceinline__ void sts_f2(uint32_t a, float x, float y) { asm volatile("st.shared.v2.f32 [%0], {%1,%2};" ::"r"(a), "f"(x), "f"(y) : "memory"); }

__device__ __forceinline__ void ldsm4(unsigned (&r)[4], uint32_t a) {
    asm volatile("ldmatrix.sync.aligned.m8n8.x4.shared.b16 {%0,%1,%2,%3}, [%4];" : "=r"(r[0]), "=r"(r[1]), "=r"(r[2]), "=r"(r[3]) : "r"(a) : "memory");
}
__device__ __forceinline__ void ldsm4t(unsigned (&r)[4], uint32_t a) {
    asm volatile("ldmatrix.sync.aligned.m8n8.x4.trans.shared.b16 {%0,%1,%2,%3}, [%4];" : "=r"(r[0]), "=r"(r[1]), "=r"(r[2]), "=r"(r[3]) : "r"(a) : "memory");
}
__device__ __forceinline__ void mma16816(float (&c)[4], const unsigned (&a)[4], unsigned b0, unsigned b1) {
    asm volatile("mma.sync.aligned.m16n8k16.row.col.f32.bf16.bf16.f32 {%0,%1,%2,%3}, {%4,%5,%6,%7}, {%8,%9}, {%0,%1,%2,%3};"
                 : "+f"(c[0]), "+f"(c[1]), "+f"(c[2]), "+f"(c[3]) : "r"(a[0]), "r"(a[1]), "r"(a[2]), "r"(a[3]), "r"(b0), "r"(b1));
}
__device__ __forceinline__ void mma1688(float (&c)[4], unsigned a0, unsigned a1, unsigned b0) {
    asm volatile("mma.sync.aligned.m16n8k8.row.col.f32.bf16.bf16.f32 {%0,%1,%2,%3}, {%4,%5}, {%6}, {%0,%1,%2,%3};"
                 : "+f"(c[0]), "+f"(c[1]), "+f"(c[2]), "+f"(c[3]) : "r"(a0), "r"(a1), "r"(b0));
}
__device__ __forceinline__ void sts_bf(uint32_t a, float v) {
    asm volatile("st.shared.u16 [%0], %1;" ::"r"(a), "h"(__bfloat16_as_ushort(__float2bfloat16_rn(v))) : "memory");
}
__device__ __forceinline__ unsigned movmat(unsigned a) {
    unsigned d; asm volatile("movmatrix.sync.aligned.m8n8.trans.b16 %0, %1;" : "=r"(d) : "r"(a)); return d;
}
__device__ __forceinline__ float warp_sum(float v) {
#pragma unroll
    for (int o = 16; o > 0; o >>= 1) v += __shfl_xor_sync(0xffffffffu, v, o);
    return v;
}

__device__ __forceinline__ void gemv32_partial(uint32_t w_base, uint32_t bar, uint32_t vec_base, uint32_t part_base, int warp, int lane) {
    const int mi = lane >> 3, ri = lane & 7;
    uint32_t wa = w_base + (16 * warp + ri + 8 * (mi >> 1)) * 64 + (((mi & 1) ^ ((ri >> 1) & 3)) << 4);
    uint32_t va = vec_base + (16 * warp + 2 * (lane & 3)) * 2;
    float c0[4] = {0.f, 0.f, 0.f, 0.f}, c1[4] = {0.f, 0.f, 0.f, 0.f};
#pragma unroll 1
    for (int i = 0; i < 4; i++) {
        const unsigned b0 = lds_u(va), b1 = lds_u(va + 16);
        mbar_wait(bar);
        unsigned a0[4], a1[4];
        ldsm4t(a0, wa);
        ldsm4t(a1, wa ^ 32);
        mma16816(c0, a0, b0, b1);
        mma16816(c1, a1, b0, b1);
        wa += BLK; va += 144 * 2; bar += 8;
    }
    const int t = lane & 3;
    const float v = t == 0 ? c0[0] : t == 1 ? c0[2] : t == 2 ? c1[0] : c1[2];
    sts_f(part_base + warp * 128 + (8 * t + (lane >> 2)) * 4, v);
}

__device__ __forceinline__ float sum9(uint32_t part_addr) {
    float v = 0.f;
#pragma unroll
    for (int w = 0; w < 9; w++) v += lds_f(part_addr + w * 128);
    return v;
}

__device__ __forceinline__ float gelu_bias(float acc, float bias) {
    const float pre = bf_round(bf_round(acc) + bias);
    const float u = 0.7978845608028654f * (pre + 0.044715f * pre * pre * pre);
    const float th = 1.f - __fdividef(2.f, __expf(2.f * u) + 1.f);
    return 0.5f * pre * (1.f + th);
}

__device__ __forceinline__ void layernorm18(float (&v)[18]) {
    float s = 0.f;
#pragma unroll
    for (int i = 0; i < 18; i++) s += v[i];
    const float mean = warp_sum(s) * (1.f / D_MODEL);
    float q = 0.f;
#pragma unroll
    for (int i = 0; i < 18; i++) { const float d = v[i] - mean; q = fmaf(d, d, q); }
    const float var = bf_round(warp_sum(q) * (1.f / D_MODEL));
    const float mb = bf_round(mean);
    const float den = bf_round(sqrtf(bf_round(var + 1e-5f)));
#pragma unroll
    for (int i = 0; i < 18; i++) v[i] = bf_round(__fdividef(bf_round(v[i] - mb), den));
}

__global__ void __launch_bounds__(NTHREADS, 1)
fused_decode_kernel(const __grid_constant__ CUtensorMap map_q, const __grid_constant__ CUtensorMap map_1,
                    const __grid_constant__ CUtensorMap map_k, const __grid_constant__ CUtensorMap map_v,
                    const __grid_constant__ CUtensorMap map_o, const __grid_constant__ CUtensorMap map_2,
                    const __nv_bfloat16* __restrict__ x, const __nv_bfloat16* __restrict__ b1,
                    const __nv_bfloat16* __restrict__ b2, __nv_bfloat16* __restrict__ out
                    ) {
    extern __shared__ __align__(1024) unsigned char smem_raw[];
    const uint32_t sm = ((uint32_t)__cvta_generic_to_shared(smem_raw) + 1023u) & ~1023u;
    const int tid = threadIdx.x, warp = tid >> 5, lane = tid & 31;
    const int cta = blockIdx.x;
    const bool is_main = cta < NMAIN;
    const int unit0 = is_main ? cta : NMAIN + (cta - NMAIN) * 4;
    const uint32_t bar0 = sm + OFF_BAR;
    constexpr float LOG2E = 1.4426950408889634f;

    if (warp == 9) {
        const unsigned tstart = gtime32();
        if (lane == 0) {
            STAMP(0);
            if (is_main) {
#pragma unroll
                for (int i = 0; i < 4; i++) mbar_init(bar0 + i * 8, 1);
                asm volatile("fence.mbarrier_init.release.cluster;" ::: "memory");
#pragma unroll
                for (int i = 0; i < 4; i++) {
                    mbar_expect_tx(bar0 + i * 8, BLK);
                    tma2d(sm + OFF_A + i * BLK, &map_q, cta * 32, i * 144, bar0 + i * 8);
                }
            } else {
#pragma unroll
                for (int i = 0; i < 4; i++) mbar_init(bar0 + i * 8, 1);
            }
#pragma unroll 4
            for (int i = 4; i < NITEM; i++) mbar_init(bar0 + i * 8, 1);
            mbar_init(bar0 + BAR_EQ * 8, 9);
            mbar_init(bar0 + BAR_EK * 8, 8);
            mbar_init(bar0 + BAR_Q * 8, 1);
            mbar_init(bar0 + BAR_EV * 8, 8);
            mbar_init(bar0 + BAR_H * 8, 1);
            mbar_init(bar0 + BAR_O * 8, 1);
            mbar_init(bar0 + BAR_Z * 8, 1);
            asm volatile("fence.mbarrier_init.release.cluster;" ::: "memory");
        }
        __syncwarp();
        bar_arrive(0, NTHREADS);
        unsigned due = tstart + T0;
        if (is_main) {
            const int row0 = (cta >> 3) * SK + (SK - WINDOW) + (cta & 7) * 32;
#pragma unroll 1
            for (int i = IT_K; i < NITEM; i++) {
                if (i >= WMAX) mbar_wait(bar0 + (i - WMAX) * 8);
                if (i >= W0) { due += i < IT_V ? TAU : i < IT_W1 ? TAUV : TAUW; pace_wait(bar0 + (i - WMIN) * 8, due); }
                if (i == IT_V + 6) mbar_wait(bar0 + BAR_EQ * 8);
                if (i == IT_V + 10) mbar_wait(bar0 + BAR_EK * 8);
                if (i == IT_W2) mbar_wait(bar0 + BAR_EV * 8);
                const uint32_t bar = bar0 + i * 8;
                const int u = (i - IT_K) & 15, j = i & 3;
                uint32_t dst = OFF_K + u * UNIT;
                if (i >= IT_V) dst = u < 6 ? OFF_B + u * UNIT : u < 10 ? OFF_A + (u - 6) * UNIT : OFF_K + (u - 10) * UNIT;
                if (i >= IT_W1) dst = (i < IT_WO ? OFF_W1 : i < IT_W2 ? OFF_WO : OFF_B) + j * BLK;
                const CUtensorMap* map = i < IT_V ? &map_k : i < IT_W1 ? &map_v : i < IT_W2 ? &map_o : &map_2;
                const int c1 = i < IT_W1 ? row0 + u * 256 : cta * 32 + j * 8;
                if (lane == 0) {
                    mbar_expect_tx(bar, i < IT_W1 ? UNIT : BLK);
                    if (i >= IT_W1 && i < IT_WO) tma2d(sm + dst, &map_1, cta * 32, j * 144, bar);
                    else tma3d(sm + dst, map, c1, bar);
                }
                __syncwarp();
            }
            STAMP(19);
        } else {
#pragma unroll 1
            for (int i = 0; i < 32; i++) {
                if (i >= WMAX) mbar_wait(bar0 + (i - WMAX) * 8);
                if (i >= W0) { due += XTAU; pace_wait(bar0 + (i - WMIN) * 8, due); }
                if (i == 20) mbar_wait(bar0 + BAR_EQ * 8);
                const uint32_t bar = bar0 + i * 8;
                if (lane == 0) {
                    mbar_expect_tx(bar, BLK);
                    if (i < 16) tma2d(sm + i * BLK, &map_1, (unit0 + (i >> 2)) * 32, (i & 3) * 144, bar);
                    else tma3d(sm + (i < 20 ? i : i - 20) * BLK, &map_2, unit0 * 32 + (i - 16) * 8, bar);
                }
                __syncwarp();
            }
        }
    } else if (warp < 9) {
        float bias[4];
        if (warp == 8) {
#pragma unroll
            for (int i = 0; i < 4; i++) bias[i] = (is_main && i > 0) ? 0.f : __bfloat162float(b1[32 * (unit0 + i) + lane]);
        }
        float res = 0.f;
        if (warp == 0 && cta < NRED && lane < 8) res = __bfloat162float(x[cta * 8 + lane]) + __bfloat162float(b2[cta * 8 + lane]);
        bar_sync(0, NTHREADS);
        const uint32_t par = lds_u(sm + OFF_PAR);
        if (warp == 0) STAMP(1);
        unsigned* pdst = &g_px[((8 * warp + 2 * (lane & 3)) * NCTA + cta) * 8 + (lane >> 2)];
        const unsigned* psrc = &g_px[cta * NCTA * 8 + tid * 4];
        asm volatile("" : "+l"(pdst), "+l"(psrc));

        if (is_main) {
            const int grp = cta >> 3, split = cta & 7;
            gemv32_partial(sm + OFF_A, bar0 + IT_Q * 8, sm + OFF_XN, sm + OFF_PART, warp, lane);
            __syncwarp();
            if (lane == 0) mbar_arrive(bar0 + BAR_EQ * 8);
            if (warp == 0) STAMP(2);
            if (warp == 8) {
                bar_sync(1, 288);
                const float v = sum9(sm + OFF_PART + lane * 4);
                const float vn = __shfl_down_sync(0xffffffffu, v, 1);
                unsigned wd = pack_bf(v, vn);
                if (wd == 0u) wd = 0x8000u;
                const int i = lane >> 1;
                if (!(lane & 1)) st_pub1(&g_qx[par][cta * 16 + (i & 3) * 4 + (i >> 2)], wd);
                STAMP(3);
                bar_arrive(5, 288);
            } else {
                bar_arrive(1, 288);
                uint4 qf[4];
                mbar_wait(bar0 + BAR_Q * 8);
#pragma unroll
                for (int p = 0; p < 4; p++) {
                    qf[p] = make_uint4(0, 0, 0, 0);
                    if (lane < 8) qf[p] = lds_u4(sm + OFF_Q + (lane >> 2) * 256 + p * 64 + (lane & 3) * 16);
                }
                if (warp == 0) STAMP(5);
                const int mi = lane >> 3, ri = lane & 7;
                const uint32_t kaddr = sm + OFF_K + warp * UNIT + (ri + 8 * (mi & 1)) * 128 + ((ri ^ (mi >> 1)) << 4);
                const uint32_t vrel = (ri + 8 * (mi >> 1)) * 128 + ((ri ^ (mi & 1)) << 4);
                float s[4][4];
#pragma unroll
                for (int c = 0; c < 4; c++) {
                    if ((c & 1) == 0) mbar_wait(bar0 + (IT_K + warp + 4 * c) * 8);
                    float s2[4] = {0.f, 0.f, 0.f, 0.f};
#pragma unroll
                    for (int k = 0; k < 4; k++) s[c][k] = 0.f;
#pragma unroll
                    for (int p = 0; p < 4; p++) {
                        unsigned a0[4], a1[4];
                        const uint32_t base = (c >> 1) * 8 * UNIT + (c & 1) * 2048 + (p >> 1) * 4096;
                        ldsm4(a0, (kaddr ^ ((p & 1) * 64)) + base);
                        ldsm4(a1, (kaddr ^ ((p & 1) * 64 + 32)) + base);
                        mma16816(s[c], a0, qf[p].x, qf[p].y);
                        mma16816(s2, a1, qf[p].z, qf[p].w);
                    }
#pragma unroll
                    for (int k = 0; k < 4; k++) s[c][k] = bf_round(bf_round(s[c][k] + s2[k]) * 0.08838834764831845f);
                    if (warp == 0 && c == 3) STAMP(9);
                }
                __syncwarp();
                if (lane == 0) mbar_arrive(bar0 + BAR_EK * 8);
                float m0 = fmaxf(fmaxf(fmaxf(s[0][0], s[0][2]), fmaxf(s[1][0], s[1][2])), fmaxf(fmaxf(s[2][0], s[2][2]), fmaxf(s[3][0], s[3][2])));
                float m1 = fmaxf(fmaxf(fmaxf(s[0][1], s[0][3]), fmaxf(s[1][1], s[1][3])), fmaxf(fmaxf(s[2][1], s[2][3]), fmaxf(s[3][1], s[3][3])));
#pragma unroll
                for (int o = 4; o <= 16; o <<= 1) {
                    m0 = fmaxf(m0, __shfl_xor_sync(0xffffffffu, m0, o));
                    m1 = fmaxf(m1, __shfl_xor_sync(0xffffffffu, m1, o));
                }
                if (lane == 0) sts_f2(sm + OFF_WM + warp * 8, m0, m1);
                bar_sync(5, 288);
#pragma unroll
                for (int w = 0; w < 4; w++) {
                    const float4 t = lds_f4(sm + OFF_WM + w * 16);
                    m0 = fmaxf(m0, fmaxf(t.x, t.z)); m1 = fmaxf(m1, fmaxf(t.y, t.w));
                }
                float l0 = 0.f, l1 = 0.f;
                unsigned pb[4][2];
#pragma unroll
                for (int c = 0; c < 4; c++) {
                    const float p0 = exp2f((s[c][0] - m0) * LOG2E), p1 = exp2f((s[c][1] - m1) * LOG2E);
                    const float p2 = exp2f((s[c][2] - m0) * LOG2E), p3 = exp2f((s[c][3] - m1) * LOG2E);
                    l0 += p0 + p2; l1 += p1 + p3;
                    pb[c][0] = movmat(pack_bf(p0, p1));
                    pb[c][1] = movmat(pack_bf(p2, p3));
                }
#pragma unroll
                for (int o = 4; o <= 16; o <<= 1) {
                    l0 += __shfl_xor_sync(0xffffffffu, l0, o);
                    l1 += __shfl_xor_sync(0xffffffffu, l1, o);
                }
                if (lane == 0) sts_f2(sm + OFF_WL + warp * 8, l0, l1);
                unsigned* odst = &g_ox[(grp * 8 + warp) * OX_WORDS];
                float o[8][4];
#pragma unroll
                for (int j = 0; j < 8; j++) { o[j][0] = o[j][1] = o[j][2] = o[j][3] = 0.f; }
#pragma unroll
                for (int uu = 0; uu < 2; uu++) {
                    const uint32_t voff = uu == 0 ? (warp < 6 ? OFF_B + warp * UNIT : OFF_A + (warp - 6) * UNIT)
                                                  : (warp < 2 ? OFF_A + (warp + 2) * UNIT : OFF_K + (warp - 2) * UNIT);
                    const uint32_t vaddr = sm + voff + vrel;
                    mbar_wait(bar0 + (IT_V + warp + 8 * uu) * 8);
#pragma unroll
                    for (int t = 0; t < 2; t++) {
#pragma unroll
                        for (int j = 0; j < 8; j++) {
                            unsigned a[4];
                            ldsm4t(a, (vaddr ^ ((j & 3) * 32)) + t * 2048 + (j >> 2) * 4096);
                            mma16816(o[j], a, pb[2 * uu + t][0], pb[2 * uu + t][1]);
                        }
                    }
                    if (uu == 0) {
                        __syncwarp();
                        if (lane == 0) mbar_arrive(bar0 + BAR_EV * 8);
                        mbar_wait(bar0 + BAR_Z * 8);
                    }
                    if (warp == 7) STAMP(10 + uu);
                }
                if ((lane & 3) == 0) {
                    const uint32_t ma = sm + OFF_MERGE + warp * 1024 + (lane >> 2) * 4;
#pragma unroll
                    for (int j = 0; j < 8; j++) {
                        sts_f(ma + j * 64, o[j][0]); sts_f(ma + 512 + j * 64, o[j][1]);
                        sts_f(ma + j * 64 + 32, o[j][2]); sts_f(ma + 512 + j * 64 + 32, o[j][3]);
                    }
                }
                bar_sync(6, 256);
                float ov = 0.f, lv = 0.f;
#pragma unroll
                for (int w = 0; w < 8; w++) {
                    ov += lds_f(sm + OFF_MERGE + w * 1024 + tid * 4);
                    lv += lds_f(sm + OFF_WL + w * 8 + (warp >> 2) * 4);
                }
                st_pub1(odst + split * 32 + lane, enc(ov));
                if (lane == 0) st_pub2(odst + 256 + split * 2, enc(warp >> 2 ? m1 : m0), enc(lv));
                if (warp == 0) STAMP(14);
            }
        }
        {
            const int nsl = is_main ? 1 : 4;
#pragma unroll 1
            for (int r = 0; r < nsl; r++) {
                const uint32_t part = sm + (is_main ? OFF_PARTH : OFF_PART + r * 1152);
                gemv32_partial(sm + (is_main ? OFF_W1 : r * SLICE), bar0 + (is_main ? IT_W1 : 4 * r) * 8, sm + OFF_Y, part, warp, lane);
                if (warp < 8) bar_arrive(8 + r, 288);
                else {
                    bar_sync(8 + r, 288);
                    const float bv = r == 0 ? bias[0] : r == 1 ? bias[1] : r == 2 ? bias[2] : bias[3];
                    sts_bf(sm + OFF_COEF + ((is_main ? 32 : 32 * r) + lane) * 2, gelu_bias(sum9(part + lane * 4), bv));
                }
            }
            __syncwarp();
            if (!is_main && lane == 0) mbar_arrive(bar0 + BAR_EQ * 8);
            if (warp == 8) {
                __syncwarp();
                if (lane == 0) mbar_arrive(bar0 + BAR_H * 8);
                STAMP(4);
            }
        }
        mbar_wait(bar0 + BAR_H * 8);
        if (warp == 0) STAMP(16);
        {
            float acc[4][4];
#pragma unroll
            for (int j = 0; j < 4; j++) { acc[j][0] = acc[j][1] = acc[j][2] = acc[j][3] = 0.f; }
            const int t = lane & 3;
            const uint32_t rel = warp * 1024 + (lane & 7) * 128 + (((lane >> 3) ^ (lane & 7)) << 4);
            auto rows8 = [&](uint32_t wa, unsigned b) {
                unsigned a0[4], a1[4];
                ldsm4t(a0, wa);
                ldsm4t(a1, wa ^ 64);
                mma1688(acc[0], a0[0], a0[1], b); mma1688(acc[1], a0[2], a0[3], b);
                mma1688(acc[2], a1[0], a1[1], b); mma1688(acc[3], a1[2], a1[3], b);
            };
            const int nblk = is_main ? 4 : 16;
            uint32_t wa = sm + (is_main ? OFF_B : 4 * SLICE) + rel;
            uint32_t ca = sm + OFF_COEF + (is_main ? 64 : 0) + t * 4;
            uint32_t bar = bar0 + (is_main ? IT_W2 : 16) * 8;
            if (is_main) {
                mbar_wait5(bar0 + IT_WO * 8, bar0 + BAR_O * 8);
#pragma unroll
                for (int k = 0; k < 4; k++) rows8(sm + OFF_WO + rel + k * BLK, lds_u(sm + OFF_COEF + t * 4 + k * 16));
                if (warp == 0) STAMP(7);
            } else mbar_wait(bar0 + BAR_Z * 8);
#pragma unroll 1
            for (int b = 0; b < nblk; b++) {
                const unsigned bc = lds_u(ca);
                mbar_wait(bar);
                rows8(wa, bc);
                wa += BLK; ca += 16; bar += 8;
                if (b == 3) wa = sm + rel;
            }
            const float vlo = t == 0 ? acc[0][0] : t == 1 ? acc[1][0] : t == 2 ? acc[2][0] : acc[3][0];
            const float vhi = t == 0 ? acc[0][2] : t == 1 ? acc[1][2] : t == 2 ? acc[2][2] : acc[3][2];
            st_pub1(pdst, enc(vlo));
            st_pub1(pdst + NCTA * 8, enc(vhi));
            if (warp == 0) STAMP(17);
        }
        if (cta < NRED) {
            uint4 p = make_uint4(0x80000000u, 0x80000000u, 0x80000000u, 0x80000000u);
            int it = 0;
            bool bad;
            do {
                if (warp < 8 || lane < 8) p = ld_poll4(psrc);
                bad = min(min(p.x, p.y), min(p.z, p.w)) == 0u;
            } while (__any_sync(0xffffffffu, bad) && ++it < (1 << 20));
            if (warp == 0) STAMP(22);
            const float t0 = __uint_as_float(p.x), t1 = __uint_as_float(p.y), t2 = __uint_as_float(p.z), t3 = __uint_as_float(p.w);
            const bool u4 = lane & 16, u3 = lane & 8;
            const float r0 = (u4 ? t2 : t0) + __shfl_xor_sync(0xffffffffu, u4 ? t0 : t2, 16);
            const float r1 = (u4 ? t3 : t1) + __shfl_xor_sync(0xffffffffu, u4 ? t1 : t3, 16);
            float r = (u3 ? r1 : r0) + __shfl_xor_sync(0xffffffffu, u3 ? r0 : r1, 8);
            r += __shfl_xor_sync(0xffffffffu, r, 4);
            r += __shfl_xor_sync(0xffffffffu, r, 2);
            if ((lane & 6) == 0) sts_f(sm + OFF_RED + warp * 32 + (4 * (lane & 1) + (u4 ? 2 : 0) + (u3 ? 1 : 0)) * 4, r);
            if (warp > 0) bar_arrive(7, 288);
            else {
                bar_sync(7, 288);
                const uint32_t ra = sm + OFF_RED + (lane & 7) * 4;
                float tot = res;
#pragma unroll
                for (int w = 0; w < 9; w++) tot += lds_f(ra + w * 32);
                if (lane < 8) out[cta * 8 + lane] = __float2bfloat16_rn(tot);
                STAMP(23);
            }
        }
    } else if (warp == 10) {
        float v[18];
        const unsigned* x32 = reinterpret_cast<const unsigned*>(x);
#pragma unroll
        for (int i = 0; i < 9; i++) { const unsigned u = __ldg(x32 + lane + 32 * i); v[2 * i] = bf_lo(u); v[2 * i + 1] = bf_hi(u); }
        const unsigned epoch = ld_poll1(&g_epoch);
        layernorm18(v);
#pragma unroll
        for (int i = 0; i < 9; i++) sts_u(sm + OFF_XN + (lane + 32 * i) * 4, pack_bf(v[2 * i], v[2 * i + 1]));
        STAMP(27);
        layernorm18(v);
#pragma unroll
        for (int i = 0; i < 9; i++) sts_u(sm + OFF_Y + (lane + 32 * i) * 4, pack_bf(v[2 * i], v[2 * i + 1]));
        const unsigned par = epoch & 1u;
        if (lane == 0) asm volatile("st.shared.u32 [%0], %1;" ::"r"(sm + OFF_PAR), "r"(par) : "memory");
        STAMP(20);
        bar_sync(0, NTHREADS);
        const uint4 z = make_uint4(0, 0, 0, 0);
        if (is_main) {
            if (lane < 4) reinterpret_cast<uint4*>(&g_qx[par ^ 1][cta * 16])[lane] = z;
#pragma unroll
            for (int i = 0; i < 3; i++)
                if (lane + 32 * i < OX_WORDS / 4) reinterpret_cast<uint4*>(&g_ox[cta * OX_WORDS])[lane + 32 * i] = z;
        }
        if (cta < NRED) {
#pragma unroll
            for (int i = 0; i < 9; i++)
                if (lane + 32 * i < NCTA * 2) reinterpret_cast<uint4*>(&g_px[cta * NCTA * 8])[lane + 32 * i] = z;
        }
        __threadfence();
        __syncwarp();
        if (lane == 0) asm volatile("red.relaxed.gpu.global.add.u32 [%0], 1;" ::"l"(&g_zcnt) : "memory");
        STAMP(25);
        const unsigned target = (epoch + 1u) * NCTA;
        unsigned cnt;
        int it = 0;
        do {
            asm volatile("ld.acquire.gpu.global.u32 %0, [%1];" : "=r"(cnt) : "l"(&g_zcnt) : "memory");
        } while ((int)(cnt - target) < 0 && ++it < (1 << 20));
        __syncwarp();
        if (lane == 0) {
            mbar_arrive(bar0 + BAR_Z * 8);
            if (cta == 0) st_pub1(&g_epoch, epoch + 1u);
        }
        STAMP(31);
    } else {
        bar_sync(0, NTHREADS);
        const unsigned par = lds_u(sm + OFF_PAR);
        if (is_main) {
            {
                const unsigned* src = &g_qx[par][(cta >> 3) * 128 + lane * 4];
                uint4 qv;
                int it = 0;
                do {
                    qv = ld_poll4(src);
                } while (!__all_sync(0xffffffffu, qv.x && qv.y && qv.z && qv.w) && ++it < (1 << 20));
                asm volatile("st.shared.v4.u32 [%0], {%1,%2,%3,%4};" ::"r"(sm + OFF_Q + lane * 16), "r"(qv.x), "r"(qv.y), "r"(qv.z), "r"(qv.w) : "memory");
                __syncwarp();
                if (lane == 0) mbar_arrive(bar0 + BAR_Q * 8);
            }
            const unsigned* src = &g_ox[cta * OX_WORDS];
            unsigned ov[8], ml = 0u;
#pragma unroll
            for (int p = 0; p < 8; p++) ov[p] = 0u;
            mbar_wait(bar0 + BAR_Z * 8);
            mbar_wait(bar0 + (IT_V + OPOLL) * 8);
            int it = 0;
            bool ok;
            do {
                if (!ml) ml = ld_poll1(src + 256 + (lane & 15));
#pragma unroll
                for (int p = 0; p < 8; p++) if (!ov[p]) ov[p] = ld_poll1(src + p * 32 + lane);
                ok = ml != 0u;
#pragma unroll
                for (int p = 0; p < 8; p++) ok = ok && ov[p];
            } while (!__all_sync(0xffffffffu, ok) && ++it < (1 << 20));
            const float mlf = __uint_as_float(ml);
            float mx = mlf;
#pragma unroll
            for (int o = 2; o <= 8; o <<= 1) mx = fmaxf(mx, __shfl_xor_sync(0xffffffffu, mx, o));
            const float wgt = exp2f((mlf - mx) * LOG2E);
            float num = 0.f, den = 0.f;
#pragma unroll
            for (int p = 0; p < 8; p++) {
                const float wp = __shfl_sync(0xffffffffu, wgt, 2 * p);
                const float lp = __shfl_sync(0xffffffffu, mlf, 2 * p + 1);
                num = fmaf(wp, __uint_as_float(ov[p]), num);
                den = fmaf(wp, lp, den);
            }
            sts_bf(sm + OFF_COEF + lane * 2, __fdividef(num, den));
            __syncwarp();
            if (lane == 0) mbar_arrive(bar0 + BAR_O * 8);
            STAMP(15);
        }
    }
}

typedef CUresult (*EncodeTiledFn)(CUtensorMap*, CUtensorMapDataType, cuuint32_t, void*, const cuuint64_t*, const cuuint64_t*,
                                  const cuuint32_t*, const cuuint32_t*, CUtensorMapInterleave, CUtensorMapSwizzle,
                                  CUtensorMapL2promotion, CUtensorMapFloatOOBfill);

}

extern "C" void kernel_launch(void* const* d_in, const int* in_sizes, int n_in, void* d_out, int out_size) {
    (void)in_sizes; (void)n_in; (void)out_size;
    static EncodeTiledFn encode = nullptr;
    if (!encode) {
        void* fn = nullptr;
        cudaDriverEntryPointQueryResult qr;
        cudaGetDriverEntryPoint("cuTensorMapEncodeTiled", &fn, cudaEnableDefault, &qr);
        encode = (EncodeTiledFn)fn;
        cudaFuncSetAttribute(fused_decode_kernel, cudaFuncAttributeMaxDynamicSharedMemorySize, SMEM_BYTES);
    }
    CUtensorMap mq, m1, mk, mv, mo, m2;
    const cuuint32_t es[3] = {1, 1, 1};
    {
        const cuuint64_t dq[2] = {QD, D_MODEL}, sq[1] = {QD * 2}, d1[2] = {FF, D_MODEL}, s1[1] = {FF * 2};
        const cuuint32_t bx[2] = {32, 144};
        encode(&mq, CU_TENSOR_MAP_DATA_TYPE_BFLOAT16, 2, d_in[3], dq, sq, bx, es, CU_TENSOR_MAP_INTERLEAVE_NONE,
               CU_TENSOR_MAP_SWIZZLE_64B, CU_TENSOR_MAP_L2_PROMOTION_L2_128B, CU_TENSOR_MAP_FLOAT_OOB_FILL_NONE);
        encode(&m1, CU_TENSOR_MAP_DATA_TYPE_BFLOAT16, 2, d_in[6], d1, s1, bx, es, CU_TENSOR_MAP_INTERLEAVE_NONE,
               CU_TENSOR_MAP_SWIZZLE_64B, CU_TENSOR_MAP_L2_PROMOTION_L2_128B, CU_TENSOR_MAP_FLOAT_OOB_FILL_NONE);
    }
    {
        const cuuint64_t d[3] = {64, (cuuint64_t)16 * SK, 2}, st[2] = {256, 128};
        const cuuint32_t bx[3] = {64, 32, 2};
        encode(&mk, CU_TENSOR_MAP_DATA_TYPE_BFLOAT16, 3, d_in[1], d, st, bx, es, CU_TENSOR_MAP_INTERLEAVE_NONE,
               CU_TENSOR_MAP_SWIZZLE_128B, CU_TENSOR_MAP_L2_PROMOTION_L2_128B, CU_TENSOR_MAP_FLOAT_OOB_FILL_NONE);
        encode(&mv, CU_TENSOR_MAP_DATA_TYPE_BFLOAT16, 3, d_in[2], d, st, bx, es, CU_TENSOR_MAP_INTERLEAVE_NONE,
               CU_TENSOR_MAP_SWIZZLE_128B, CU_TENSOR_MAP_L2_PROMOTION_L2_128B, CU_TENSOR_MAP_FLOAT_OOB_FILL_NONE);
    }
    {
        const cuuint64_t dOo[3] = {64, QD, 9}, d2[3] = {64, FF, 9}, st[2] = {D_MODEL * 2, 128};
        const cuuint32_t bx[3] = {64, 8, 9};
        encode(&mo, CU_TENSOR_MAP_DATA_TYPE_BFLOAT16, 3, d_in[4], dOo, st, bx, es, CU_TENSOR_MAP_INTERLEAVE_NONE,
               CU_TENSOR_MAP_SWIZZLE_128B, CU_TENSOR_MAP_L2_PROMOTION_L2_128B, CU_TENSOR_MAP_FLOAT_OOB_FILL_NONE);
        encode(&m2, CU_TENSOR_MAP_DATA_TYPE_BFLOAT16, 3, d_in[8], d2, st, bx, es, CU_TENSOR_MAP_INTERLEAVE_NONE,
               CU_TENSOR_MAP_SWIZZLE_128B, CU_TENSOR_MAP_L2_PROMOTION_L2_128B, CU_TENSOR_MAP_FLOAT_OOB_FILL_NONE);
    }
    fused_decode_kernel<<<NCTA, NTHREADS, SMEM_BYTES>>>(
        mq, m1, mk, mv, mo, m2, (const __nv_bfloat16*)d_in[0], (const __nv_bfloat16*)d_in[7],
        (const __nv_bfloat16*)d_in[9], (__nv_bfloat16*)d_out
        );
}
```

```cpp
#include <cuda_runtime.h>
#include <cuda.h>
#include <cuda_bf16.h>
#include <stdint.h>
#include <math.h>

namespace {

constexpr int D_MODEL = 576;
constexpr int SK = 16384, WINDOW = 4096;
constexpr int QD = 4096, FF = 4608;
constexpr int NCTA = 132, NMAIN = 128;
constexpr int NPROD = 2;
constexpr int W_LN = 9, W_RX = 10, W_P0 = 11;
constexpr int NTHREADS = (W_P0 + NPROD) * 32;
constexpr int SLICE = 36864;
constexpr int BLK = SLICE / 4;
constexpr int WOBLK = SLICE / 3;
constexpr int UNIT = 8192;

constexpr int OFF_A = 0;
constexpr int OFF_K = OFF_A + SLICE;
constexpr int OFF_B = OFF_K + 16 * UNIT;
constexpr int OFF_W1 = OFF_K + 6 * UNIT;
constexpr int OFF_WO = OFF_W1 + SLICE;
constexpr int OFF_MERGE = OFF_B + 6 * UNIT;
constexpr int OFF_PART = OFF_MERGE;
constexpr int OFF_XN = OFF_MERGE + 8192;
constexpr int OFF_Y = OFF_XN + 1152;
constexpr int OFF_PARTH = OFF_Y + 1152;
constexpr int OFF_COEF = OFF_PARTH + 1152;
constexpr int OFF_Q = OFF_COEF + 256;
constexpr int OFF_WM = OFF_Q + 512;
constexpr int OFF_WL = OFF_WM + 64;
constexpr int OFF_PAR = OFF_WL + 64;
constexpr int OFF_BAR = OFF_PAR + 16;
constexpr int IT_Q = 0, IT_K = 4, IT_V = 20, IT_W1 = 36, IT_W2 = 40, IT_WO = 44, NITEM = 47;
constexpr int BAR_EQ = 48, BAR_EK = 49, BAR_EV = 50, BAR_H = 51, BAR_Q = 52, BAR_O = 53, BAR_Z = 54, NBAR = 55;
constexpr int SMEM_BYTES = OFF_BAR + NBAR * 8 + 1024;
static_assert(SMEM_BYTES <= 232448, "smem");
static_assert(OFF_WO + SLICE <= OFF_B, "smem map");

constexpr int W0 = 5;
constexpr int WMIN = 4;
constexpr int WMAX = 6;
constexpr int T0 = 600;
constexpr int TAU = 350;
constexpr int TAUW = 394;
constexpr int XTAU = 330;
constexpr int IT_OPOLL = IT_W1 + 2;

constexpr int OX_WORDS = 288;

__device__ unsigned g_epoch;
__device__ unsigned g_zcnt;
__device__ __align__(128) unsigned g_qx[2][NMAIN * 16];
__device__ __align__(128) unsigned g_ox[NMAIN * OX_WORDS];
__device__ __align__(4096) float4 g_acc[108 * 16];
#define ASLOT(t) (((t) >> 1) * 16 + ((t) & 1))

__device__ __forceinline__ unsigned gtime32() { unsigned t; asm volatile("mov.u32 %0, %%globaltimer_lo;" : "=r"(t)); return t; }

__device__ __forceinline__ void mbar_init(uint32_t bar, int cnt) {
    asm volatile("mbarrier.init.shared::cta.b64 [%0], %1;" ::"r"(bar), "r"(cnt) : "memory");
}
__device__ __forceinline__ void mbar_expect_tx(uint32_t bar, uint32_t bytes) {
    asm volatile("mbarrier.arrive.expect_tx.shared::cta.b64 _, [%0], %1;" ::"r"(bar), "r"(bytes) : "memory");
}
__device__ __forceinline__ void mbar_arrive(uint32_t bar) {
    asm volatile("mbarrier.arrive.shared::cta.b64 _, [%0];" ::"r"(bar) : "memory");
}
__device__ __forceinline__ void mbar_wait(uint32_t bar) {
    asm volatile("{\n .reg .pred p;\n .reg .u32 c;\n"
                 " mbarrier.try_wait.parity.shared::cta.b64 p, [%0], 0;\n @p bra.uni D_%=;\n mov.u32 c, 0;\n"
                 "L_%=:\n mbarrier.try_wait.parity.shared::cta.b64 p, [%0], 0;\n @p bra.uni D_%=;\n"
                 " add.u32 c, c, 1;\n setp.lt.u32 p, c, 262144;\n @p bra.uni L_%=;\n D_%=:\n}"
                 ::"r"(bar) : "memory");
}
__device__ __forceinline__ void pace_wait(uint32_t bar, unsigned due) {
    asm volatile("{\n .reg .pred p;\n .reg .u32 t;\n"
                 "L_%=:\n mbarrier.test_wait.parity.shared::cta.b64 p, [%0], 0;\n @p bra.uni D_%=;\n"
                 " mov.u32 t, %%globaltimer_lo;\n sub.u32 t, t, %1;\n setp.lt.s32 p, t, 0;\n @p bra.uni L_%=;\n D_%=:\n}"
                 ::"r"(bar), "r"(due) : "memory");
}
__device__ __forceinline__ void tma2d(uint32_t dst, const CUtensorMap* m, int c0, int c1, uint32_t bar, uint64_t pol) {
    asm volatile("cp.async.bulk.tensor.2d.shared::cluster.global.mbarrier::complete_tx::bytes.L2::cache_hint [%0], [%1, {%3, %4}], [%2], %5;"
                 ::"r"(dst), "l"(m), "r"(bar), "r"(c0), "r"(c1), "l"(pol) : "memory");
}
__device__ __forceinline__ void tma3d(uint32_t dst, const CUtensorMap* m, int c1, int c2, uint32_t bar, uint64_t pol) {
    asm volatile("cp.async.bulk.tensor.3d.shared::cluster.global.mbarrier::complete_tx::bytes.L2::cache_hint [%0], [%1, {%4, %3, %6}], [%2], %5;"
                 ::"r"(dst), "l"(m), "r"(bar), "r"(c1), "r"(0), "l"(pol), "r"(c2) : "memory");
}
__device__ __forceinline__ void bar_sync(int id, int n) { asm volatile("bar.sync %0, %1;" ::"r"(id), "r"(n) : "memory"); }
__device__ __forceinline__ void bar_arrive(int id, int n) { asm volatile("bar.arrive %0, %1;" ::"r"(id), "r"(n) : "memory"); }

__device__ __forceinline__ uint4 ld_poll4(const unsigned* p) {
    uint4 v;
    asm volatile("ld.relaxed.gpu.global.v4.u32 {%0,%1,%2,%3}, [%4];" : "=r"(v.x), "=r"(v.y), "=r"(v.z), "=r"(v.w) : "l"(p) : "memory");
    return v;
}
__device__ __forceinline__ unsigned ld_poll1(const unsigned* p) {
    unsigned v;
    asm volatile("ld.relaxed.gpu.global.u32 %0, [%1];" : "=r"(v) : "l"(p) : "memory");
    return v;
}
__device__ __forceinline__ void st_pub1(unsigned* p, unsigned v) {
    asm volatile("st.relaxed.gpu.global.u32 [%0], %1;" ::"l"(p), "r"(v) : "memory");
}
__device__ __forceinline__ void st_pub2(unsigned* p, unsigned a, unsigned b) {
    asm volatile("st.relaxed.gpu.global.v2.u32 [%0], {%1,%2};" ::"l"(p), "r"(a), "r"(b) : "memory");
}
__device__ __forceinline__ unsigned enc(float v) { unsigned u = __float_as_uint(v); return u == 0u ? 0x80000000u : u; }

__device__ __forceinline__ float bf_lo(unsigned u) { return __uint_as_float(u << 16); }
__device__ __forceinline__ float bf_hi(unsigned u) { return __uint_as_float(u & 0xffff0000u); }
__device__ __forceinline__ float bf_round(float v) { return __bfloat162float(__float2bfloat16_rn(v)); }
__device__ __forceinline__ unsigned pack_bf(float lo, float hi) {
    unsigned r; asm("cvt.rn.bf16x2.f32 %0, %1, %2;" : "=r"(r) : "f"(hi), "f"(lo)); return r;
}
__device__ __forceinline__ float lds_f(uint32_t a) { float v; asm volatile("ld.shared.f32 %0, [%1];" : "=f"(v) : "r"(a)); return v; }
__device__ __forceinline__ unsigned lds_u(uint32_t a) { unsigned v; asm volatile("ld.shared.u32 %0, [%1];" : "=r"(v) : "r"(a)); return v; }
__device__ __forceinline__ float4 lds_f4(uint32_t a) {
    float4 v; asm volatile("ld.shared.v4.f32 {%0,%1,%2,%3}, [%4];" : "=f"(v.x), "=f"(v.y), "=f"(v.z), "=f"(v.w) : "r"(a)); return v;
}
__device__ __forceinline__ uint4 lds_u4(uint32_t a) {
    uint4 v; asm volatile("ld.shared.v4.u32 {%0,%1,%2,%3}, [%4];" : "=r"(v.x), "=r"(v.y), "=r"(v.z), "=r"(v.w) : "r"(a)); return v;
}
__device__ __forceinline__ void sts_f(uint32_t a, float v) { asm volatile("st.shared.f32 [%0], %1;" ::"r"(a), "f"(v) : "memory"); }
__device__ __forceinline__ void sts_u(uint32_t a, unsigned v) { asm volatile("st.shared.u32 [%0], %1;" ::"r"(a), "r"(v) : "memory"); }
__device__ __forceinline__ void sts_f2(uint32_t a, float x, float y) { asm volatile("st.shared.v2.f32 [%0], {%1,%2};" ::"r"(a), "f"(x), "f"(y) : "memory"); }
__device__ __forceinline__ void sts_bf(uint32_t a, float v) {
    asm volatile("st.shared.u16 [%0], %1;" ::"r"(a), "h"(__bfloat16_as_ushort(__float2bfloat16_rn(v))) : "memory");
}
__device__ __forceinline__ void ldsm4(unsigned (&r)[4], uint32_t a) {
    asm volatile("ldmatrix.sync.aligned.m8n8.x4.shared.b16 {%0,%1,%2,%3}, [%4];" : "=r"(r[0]), "=r"(r[1]), "=r"(r[2]), "=r"(r[3]) : "r"(a) : "memory");
}
__device__ __forceinline__ void ldsm4t(unsigned (&r)[4], uint32_t a) {
    asm volatile("ldmatrix.sync.aligned.m8n8.x4.trans.shared.b16 {%0,%1,%2,%3}, [%4];" : "=r"(r[0]), "=r"(r[1]), "=r"(r[2]), "=r"(r[3]) : "r"(a) : "memory");
}
__device__ __forceinline__ void mma16816(float (&c)[4], const unsigned (&a)[4], unsigned b0, unsigned b1) {
    asm volatile("mma.sync.aligned.m16n8k16.row.col.f32.bf16.bf16.f32 {%0,%1,%2,%3}, {%4,%5,%6,%7}, {%8,%9}, {%0,%1,%2,%3};"
                 : "+f"(c[0]), "+f"(c[1]), "+f"(c[2]), "+f"(c[3]) : "r"(a[0]), "r"(a[1]), "r"(a[2]), "r"(a[3]), "r"(b0), "r"(b1));
}
__device__ __forceinline__ void mma1688(float (&c)[4], unsigned a0, unsigned a1, unsigned b0) {
    asm volatile("mma.sync.aligned.m16n8k8.row.col.f32.bf16.bf16.f32 {%0,%1,%2,%3}, {%4,%5}, {%6}, {%0,%1,%2,%3};"
                 : "+f"(c[0]), "+f"(c[1]), "+f"(c[2]), "+f"(c[3]) : "r"(a0), "r"(a1), "r"(b0));
}
__device__ __forceinline__ unsigned movmat(unsigned a) {
    unsigned d; asm volatile("movmatrix.sync.aligned.m8n8.trans.b16 %0, %1;" : "=r"(d) : "r"(a)); return d;
}
__device__ __forceinline__ float warp_sum(float v) {
#pragma unroll
    for (int o = 16; o > 0; o >>= 1) v += __shfl_xor_sync(0xffffffffu, v, o);
    return v;
}

__device__ __forceinline__ void gemv32_partial(uint32_t w_base, uint32_t bar, uint32_t vec_base, uint32_t part_base, int warp, int lane) {
    const int mi = lane >> 3, ri = lane & 7;
    uint32_t wa = w_base + (16 * warp + ri + 8 * (mi >> 1)) * 64 + (((mi & 1) ^ ((ri >> 1) & 3)) << 4);
    uint32_t va = vec_base + (16 * warp + 2 * (lane & 3)) * 2;
    float c0[4] = {0.f, 0.f, 0.f, 0.f}, c1[4] = {0.f, 0.f, 0.f, 0.f};
#pragma unroll 1
    for (int i = 0; i < 4; i++) {
        const unsigned b0 = lds_u(va), b1 = lds_u(va + 16);
        mbar_wait(bar);
        unsigned a0[4], a1[4];
        ldsm4t(a0, wa);
        ldsm4t(a1, wa ^ 32);
        mma16816(c0, a0, b0, b1);
        mma16816(c1, a1, b0, b1);
        wa += BLK; va += 144 * 2; bar += 8;
    }
    const int t = lane & 3;
    const float v = t == 0 ? c0[0] : t == 1 ? c0[2] : t == 2 ? c1[0] : c1[2];
    sts_f(part_base + warp * 128 + (8 * t + (lane >> 2)) * 4, v);
}

__device__ __forceinline__ float sum9(uint32_t part_addr) {
    float v = 0.f;
#pragma unroll
    for (int w = 0; w < 9; w++) v += lds_f(part_addr + w * 128);
    return v;
}

__device__ __forceinline__ float gelu_bias(float acc, float bias) {
    const float pre = bf_round(bf_round(acc) + bias);
    const float u = 0.7978845608028654f * (pre + 0.044715f * pre * pre * pre);
    const float th = 1.f - __fdividef(2.f, __expf(2.f * u) + 1.f);
    return 0.5f * pre * (1.f + th);
}

__device__ __forceinline__ void layernorm18(float (&v)[18]) {
    float s = 0.f;
#pragma unroll
    for (int i = 0; i < 18; i++) s += v[i];
    const float mean = warp_sum(s) * (1.f / D_MODEL);
    float q = 0.f;
#pragma unroll
    for (int i = 0; i < 18; i++) { const float d = v[i] - mean; q = fmaf(d, d, q); }
    const float var = bf_round(warp_sum(q) * (1.f / D_MODEL));
    const float mb = bf_round(mean);
    const float den = bf_round(sqrtf(bf_round(var + 1e-5f)));
#pragma unroll
    for (int i = 0; i < 18; i++) v[i] = bf_round(__fdividef(bf_round(v[i] - mb), den));
}

constexpr int NB_START = 0;
constexpr int NB_QPART = 1;
constexpr int NB_INIT = 2;
constexpr int NB_MAX = 5;
constexpr int NB_MERGE = 6;
constexpr int NB_HPART = 8;
constexpr int N_START = 9 * 32 + 3 * 32;
constexpr int N_INIT = (NPROD + 1) * 32;

__global__ void __launch_bounds__(NTHREADS, 1)
fused_decode_kernel(const __grid_constant__ CUtensorMap map_q, const __grid_constant__ CUtensorMap map_1,
                    const __grid_constant__ CUtensorMap map_k, const __grid_constant__ CUtensorMap map_v,
                    const __grid_constant__ CUtensorMap map_o, const __grid_constant__ CUtensorMap map_2,
                    const __nv_bfloat16* __restrict__ x, const __nv_bfloat16* __restrict__ b1,
                    const __nv_bfloat16* __restrict__ b2, __nv_bfloat16* __restrict__ out) {
    extern __shared__ __align__(1024) unsigned char smem_raw[];
    const uint32_t sm = ((uint32_t)__cvta_generic_to_shared(smem_raw) + 1023u) & ~1023u;
    const int hw = threadIdx.x >> 5, lane = threadIdx.x & 31;
    const int cta = blockIdx.x;
    const bool is_main = cta < NMAIN;
    const int unit0 = is_main ? cta : NMAIN + (cta - NMAIN) * 4;
    const uint32_t bar0 = sm + OFF_BAR;
    constexpr float LOG2E = 1.4426950408889634f;

    if (hw >= W_P0) {
        const int prod = hw - W_P0;
        const unsigned tstart = gtime32();
        uint64_t pol, pol2;
        asm volatile("createpolicy.fractional.L2::evict_first.b64 %0, 1.0;" : "=l"(pol));
        asm volatile("createpolicy.fractional.L2::evict_normal.b64 %0, 1.0;" : "=l"(pol2));
        const int nitem = is_main ? NITEM : 32;
        if (prod == 0) {
            if (lane == 0) {
#pragma unroll
                for (int i = 0; i < 4; i++) mbar_init(bar0 + i * 8, 1);
                asm volatile("fence.mbarrier_init.release.cluster;" ::: "memory");
#pragma unroll
                for (int i = 0; i < 4; i++) {
                    mbar_expect_tx(bar0 + i * 8, BLK);
                    tma2d(sm + i * BLK, is_main ? &map_q : &map_1, unit0 * 32, i * 144, bar0 + i * 8, pol2);
                }
#pragma unroll
                for (int i = 4; i < NBAR; i++) mbar_init(bar0 + i * 8, i == BAR_EQ ? 9 : (i == BAR_EK || i == BAR_EV) ? 8 : 1);
                asm volatile("fence.mbarrier_init.release.cluster;" ::: "memory");
            }
            __syncwarp();
#pragma unroll
            for (int h = 0; h < 2; h++) {
                const int i = 4 + lane + 32 * h;
                if (i < nitem) mbar_expect_tx(bar0 + i * 8, !is_main ? BLK : i < IT_W1 ? UNIT : i < IT_WO ? BLK : WOBLK);
            }
            __syncwarp();
            bar_arrive(NB_INIT, N_INIT);
            bar_arrive(NB_START, N_START);
        } else {
            bar_sync(NB_INIT, N_INIT);
        }
        const int row0 = (cta >> 3) * SK + (SK - WINDOW) + (cta & 7) * 32;
#pragma unroll 1
        for (int i = 4 + (prod + NPROD - 1) % NPROD; i < nitem; i += NPROD) {
            const uint32_t bar = bar0 + i * 8;
            uint32_t dst, gate = bar0 + BAR_EQ * 8;
            const CUtensorMap* map;
            int c1, c2 = 0, due;
            bool gated, is2d;
            if (is_main) {
                const int u = (i - IT_K) & 15, j = i & 3;
                dst = OFF_K + u * UNIT;
                if (i >= IT_V) dst = u < 6 ? OFF_B + u * UNIT : u < 10 ? OFF_A + (u - 6) * UNIT : OFF_K + (u - 10) * UNIT;
                if (i >= IT_W1) dst = (i < IT_W2 ? OFF_W1 : OFF_B) + j * BLK;
                if (i >= IT_WO) { c2 = (i - IT_WO + cta) % 3; dst = OFF_WO + c2 * WOBLK; c2 *= 3; }
                map = i < IT_V ? &map_k : i < IT_W1 ? &map_v : i < IT_W2 ? &map_1 : i < IT_WO ? &map_2 : &map_o;
                is2d = i >= IT_W1 && i < IT_W2;
                c1 = i < IT_W1 ? row0 + u * 256 : is2d ? j * 144 : i < IT_WO ? cta * 32 + j * 8 : cta * 32;
                gated = i >= IT_V + 6;
                if (i >= IT_V + 10) gate = bar0 + ((i >= IT_W2 && i < IT_WO) ? BAR_EV : BAR_EK) * 8;
                due = (i - W0 + 1) * TAU + max(0, i - IT_W1 + 1) * (TAUW - TAU) + max(0, i - IT_WO) * (TAUW / 3);
            } else {
                is2d = i < 16;
                dst = (i < 20 ? i : i - 20) * BLK;
                map = is2d ? &map_1 : &map_2;
                c1 = is2d ? (i & 3) * 144 : unit0 * 32 + (i - 16) * 8;
                gated = i >= 20;
                due = (i - W0 + 1) * XTAU;
            }
            const int c0 = (is_main ? cta : unit0 + (i >> 2)) * 32;
            if (gated) mbar_wait(gate);
            if (i >= WMAX) mbar_wait(bar - WMAX * 8);
            if (i >= W0) pace_wait(bar - WMIN * 8, tstart + T0 + due);
            if (lane == 0) {
                if (is2d) tma2d(sm + dst, map, c0, c1, bar, pol2);
                else tma3d(sm + dst, map, c1, c2, bar, pol);
            }
            __syncwarp();
        }
    } else if (hw == W_LN) {
        float v[18];
        const unsigned* x32 = reinterpret_cast<const unsigned*>(x);
#pragma unroll
        for (int i = 0; i < 9; i++) { const unsigned u = __ldg(x32 + lane + 32 * i); v[2 * i] = bf_lo(u); v[2 * i + 1] = bf_hi(u); }
        layernorm18(v);
#pragma unroll
        for (int i = 0; i < 9; i++) sts_u(sm + OFF_XN + (lane + 32 * i) * 4, pack_bf(v[2 * i], v[2 * i + 1]));
        layernorm18(v);
#pragma unroll
        for (int i = 0; i < 9; i++) sts_u(sm + OFF_Y + (lane + 32 * i) * 4, pack_bf(v[2 * i], v[2 * i + 1]));
        bar_arrive(NB_START, N_START);
    } else if (hw == W_RX) {
        const unsigned epoch = ld_poll1(&g_epoch);
        const uint4 z = make_uint4(0, 0, 0, 0);
        if (is_main) {
#pragma unroll
            for (int i = 0; i < 3; i++)
                if (lane + 32 * i < OX_WORDS / 4) reinterpret_cast<uint4*>(&g_ox[cta * OX_WORDS])[lane + 32 * i] = z;
        }
        bar_sync(NB_INIT, N_INIT);
        if (cta < 9 && (lane & 3) < 3) {
            const int col = 64 * cta + 24 * (lane & 3) + (lane >> 2), col2 = (lane & 3) < 2 ? col + 16 : col;
            g_acc[ASLOT(cta * 24 + (lane >> 2) * 3 + (lane & 3))] =
                make_float4(__bfloat162float(x[col]) + __bfloat162float(b2[col]), __bfloat162float(x[col + 8]) + __bfloat162float(b2[col + 8]),
                            __bfloat162float(x[col2]) + __bfloat162float(b2[col2]), 0.f);
        }
        const unsigned par = epoch & 1u;
        if (lane == 0) sts_u(sm + OFF_PAR, par);
        __syncwarp();
        bar_arrive(NB_START, N_START);
        if (is_main && lane < 4) reinterpret_cast<uint4*>(&g_qx[par ^ 1][cta * 16])[lane] = z;
        __threadfence();
        __syncwarp();
        if (lane == 0) asm volatile("red.relaxed.gpu.global.add.u32 [%0], 1;" ::"l"(&g_zcnt) : "memory");
        if (is_main) {
            const unsigned* src = &g_qx[par][(cta >> 3) * 128 + lane * 4];
            uint4 qv;
            int it = 0;
            do {
                qv = ld_poll4(src);
            } while (__any_sync(0xffffffffu, min(min(qv.x, qv.y), min(qv.z, qv.w)) == 0u) && ++it < (1 << 20));
            asm volatile("st.shared.v4.u32 [%0], {%1,%2,%3,%4};" ::"r"(sm + OFF_Q + lane * 16), "r"(qv.x), "r"(qv.y), "r"(qv.z), "r"(qv.w) : "memory");
            __syncwarp();
            if (lane == 0) mbar_arrive(bar0 + BAR_Q * 8);
        }
        {
            const unsigned target = (epoch + 1u) * NCTA;
            unsigned cnt;
            int it = 0;
            do {
                asm volatile("ld.acquire.gpu.global.u32 %0, [%1];" : "=r"(cnt) : "l"(&g_zcnt) : "memory");
            } while ((int)(cnt - target) < 0 && ++it < (1 << 20));
            __syncwarp();
            if (lane == 0) {
                mbar_arrive(bar0 + BAR_Z * 8);
                if (cta == 0) st_pub1(&g_epoch, epoch + 1u);
            }
        }
        if (is_main) {
            const unsigned* src = &g_ox[cta * OX_WORDS];
            unsigned ov[8], ml = 0u;
#pragma unroll
            for (int p = 0; p < 8; p++) ov[p] = 0u;
            mbar_wait(bar0 + IT_OPOLL * 8);
            int it = 0;
            unsigned mn;
            do {
                if (!ml) ml = ld_poll1(src + 256 + (lane & 15));
#pragma unroll
                for (int p = 0; p < 8; p++) if (!ov[p]) ov[p] = ld_poll1(src + p * 32 + lane);
                mn = min(min(min(ov[0], ov[1]), min(ov[2], ov[3])), min(min(min(ov[4], ov[5]), min(ov[6], ov[7])), ml));
            } while (__any_sync(0xffffffffu, mn == 0u) && ++it < (1 << 20));
            const float mlf = __uint_as_float(ml);
            float mx = mlf;
#pragma unroll
            for (int o = 2; o <= 8; o <<= 1) mx = fmaxf(mx, __shfl_xor_sync(0xffffffffu, mx, o));
            const float wgt = exp2f((mlf - mx) * LOG2E);
            float num = 0.f, den = 0.f;
#pragma unroll
            for (int p = 0; p < 8; p++) {
                const float wp = __shfl_sync(0xffffffffu, wgt, 2 * p);
                const float lp = __shfl_sync(0xffffffffu, mlf, 2 * p + 1);
                num = fmaf(wp, __uint_as_float(ov[p]), num);
                den = fmaf(wp, lp, den);
            }
            sts_bf(sm + OFF_COEF + lane * 2, __fdividef(num, den));
            __syncwarp();
            if (lane == 0) mbar_arrive(bar0 + BAR_O * 8);
        }
    } else {
        const int warp = hw, tid = threadIdx.x;
        float bias[4];
        if (warp == 8) {
#pragma unroll
            for (int i = 0; i < 4; i++) bias[i] = (is_main && i > 0) ? 0.f : __bfloat162float(b1[32 * (unit0 + i) + lane]);
        }
        float4* adst = &g_acc[ASLOT(warp * 24 + (lane >> 2) * 3 + (lane & 3))];
        __nv_bfloat16* odst2 = out + 64 * warp + 24 * (lane & 3) + (lane >> 2);
        asm volatile("" : "+l"(adst), "+l"(odst2));
        bar_sync(NB_START, N_START);

        if (is_main) {
            const int grp = cta >> 3, split = cta & 7;
            gemv32_partial(sm + OFF_A, bar0 + IT_Q * 8, sm + OFF_XN, sm + OFF_PART, warp, lane);
            __syncwarp();
            if (lane == 0) mbar_arrive(bar0 + BAR_EQ * 8);
            if (warp == 8) {
                const uint32_t par = lds_u(sm + OFF_PAR);
                bar_sync(NB_QPART, 288);
                const float v = sum9(sm + OFF_PART + lane * 4);
                const float vn = __shfl_down_sync(0xffffffffu, v, 1);
                unsigned wd = pack_bf(v, vn);
                if (wd == 0u) wd = 0x8000u;
                const int i = lane >> 1;
                if (!(lane & 1)) st_pub1(&g_qx[par][cta * 16 + (i & 3) * 4 + (i >> 2)], wd);
                bar_arrive(NB_MAX, 288);
            } else {
                bar_arrive(NB_QPART, 288);
                uint4 qf[4];
                mbar_wait(bar0 + BAR_Q * 8);
#pragma unroll
                for (int p = 0; p < 4; p++)
                    qf[p] = lds_u4(sm + OFF_Q + ((lane >> 2) & 1) * 256 + p * 64 + (lane & 3) * 16);
                const int mi = lane >> 3, ri = lane & 7;
                const uint32_t kaddr = sm + OFF_K + warp * UNIT + (ri + 8 * (mi & 1)) * 128 + ((ri ^ (mi >> 1)) << 4);
                const uint32_t vrel = (ri + 8 * (mi >> 1)) * 128 + ((ri ^ (mi & 1)) << 4);
                float s[4][4];
#pragma unroll
                for (int c = 0; c < 4; c++) {
                    if ((c & 1) == 0) mbar_wait(bar0 + (IT_K + warp + 4 * c) * 8);
                    float s2[4] = {0.f, 0.f, 0.f, 0.f};
#pragma unroll
                    for (int k = 0; k < 4; k++) s[c][k] = 0.f;
#pragma unroll
                    for (int p = 0; p < 4; p++) {
                        unsigned a0[4], a1[4];
                        const uint32_t base = (c >> 1) * 8 * UNIT + (c & 1) * 2048 + (p >> 1) * 4096;
                        ldsm4(a0, (kaddr ^ ((p & 1) * 64)) + base);
                        ldsm4(a1, (kaddr ^ ((p & 1) * 64 + 32)) + base);
                        mma16816(s[c], a0, qf[p].x, qf[p].y);
                        mma16816(s2, a1, qf[p].z, qf[p].w);
                    }
#pragma unroll
                    for (int k = 0; k < 4; k++) s[c][k] = bf_round(bf_round(s[c][k] + s2[k]) * 0.08838834764831845f);
                }
                __syncwarp();
                if (lane == 0) mbar_arrive(bar0 + BAR_EK * 8);
                float m0 = fmaxf(fmaxf(fmaxf(s[0][0], s[0][2]), fmaxf(s[1][0], s[1][2])), fmaxf(fmaxf(s[2][0], s[2][2]), fmaxf(s[3][0], s[3][2])));
                float m1 = fmaxf(fmaxf(fmaxf(s[0][1], s[0][3]), fmaxf(s[1][1], s[1][3])), fmaxf(fmaxf(s[2][1], s[2][3]), fmaxf(s[3][1], s[3][3])));
#pragma unroll
                for (int o = 4; o <= 16; o <<= 1) {
                    m0 = fmaxf(m0, __shfl_xor_sync(0xffffffffu, m0, o));
                    m1 = fmaxf(m1, __shfl_xor_sync(0xffffffffu, m1, o));
                }
                if (lane == 0) sts_f2(sm + OFF_WM + warp * 8, m0, m1);
                bar_sync(NB_MAX, 288);
#pragma unroll
                for (int w = 0; w < 4; w++) {
                    const float4 t = lds_f4(sm + OFF_WM + w * 16);
                    m0 = fmaxf(m0, fmaxf(t.x, t.z)); m1 = fmaxf(m1, fmaxf(t.y, t.w));
                }
                float l0 = 0.f, l1 = 0.f;
                unsigned pb[4][2];
#pragma unroll
                for (int c = 0; c < 4; c++) {
                    const float p0 = exp2f((s[c][0] - m0) * LOG2E), p1 = exp2f((s[c][1] - m1) * LOG2E);
                    const float p2 = exp2f((s[c][2] - m0) * LOG2E), p3 = exp2f((s[c][3] - m1) * LOG2E);
                    l0 += p0 + p2; l1 += p1 + p3;
                    pb[c][0] = movmat(pack_bf(p0, p1));
                    pb[c][1] = movmat(pack_bf(p2, p3));
                }
#pragma unroll
                for (int o = 4; o <= 16; o <<= 1) {
                    l0 += __shfl_xor_sync(0xffffffffu, l0, o);
                    l1 += __shfl_xor_sync(0xffffffffu, l1, o);
                }
                if (lane == 0) sts_f2(sm + OFF_WL + warp * 8, l0, l1);
                unsigned* odst = &g_ox[(grp * 8 + warp) * OX_WORDS];
                float o[8][4];
#pragma unroll
                for (int j = 0; j < 8; j++) { o[j][0] = o[j][1] = o[j][2] = o[j][3] = 0.f; }
#pragma unroll
                for (int uu = 0; uu < 2; uu++) {
                    const uint32_t voff = uu == 0 ? (warp < 6 ? OFF_B + warp * UNIT : OFF_A + (warp - 6) * UNIT)
                                                  : (warp < 2 ? OFF_A + (warp + 2) * UNIT : OFF_K + (warp - 2) * UNIT);
                    const uint32_t vaddr = sm + voff + vrel;
                    mbar_wait(bar0 + (IT_V + warp + 8 * uu) * 8);
#pragma unroll
                    for (int t = 0; t < 2; t++) {
#pragma unroll
                        for (int j = 0; j < 8; j++) {
                            unsigned a[4];
                            ldsm4t(a, (vaddr ^ ((j & 3) * 32)) + t * 2048 + (j >> 2) * 4096);
                            mma16816(o[j], a, pb[2 * uu + t][0], pb[2 * uu + t][1]);
                        }
                    }
                    if (uu == 0) {
                        __syncwarp();
                        if (lane == 0) mbar_arrive(bar0 + BAR_EV * 8);
                        mbar_wait(bar0 + BAR_Z * 8);
                    }
                }
                {
                    const int t4 = lane & 3;
                    const uint32_t ma = sm + OFF_MERGE + warp * 1024 + (16 * t4 + (lane >> 2)) * 8;
#pragma unroll
                    for (int h = 0; h < 2; h++) {
                        float e[4];
#pragma unroll
                        for (int k = 0; k < 4; k++)
                            e[k] = t4 == 0 ? o[4 * h][k] : t4 == 1 ? o[4 * h + 1][k] : t4 == 2 ? o[4 * h + 2][k] : o[4 * h + 3][k];
                        sts_f2(ma + h * 512, e[0], e[1]);
                        sts_f2(ma + h * 512 + 64, e[2], e[3]);
                    }
                }
                bar_sync(NB_MERGE, 256);
                float ov = 0.f, lv = 0.f;
#pragma unroll
                for (int w = 0; w < 8; w++) {
                    ov += lds_f(sm + OFF_MERGE + w * 1024 + (tid & 127) * 8 + (warp >> 2) * 4);
                    lv += lds_f(sm + OFF_WL + w * 8 + (warp >> 2) * 4);
                }
                st_pub1(odst + split * 32 + lane, enc(ov));
                if (lane == 0) st_pub2(odst + 256 + split * 2, enc(warp >> 2 ? m1 : m0), enc(lv));
            }
        }
        {
            const int nsl = is_main ? 1 : 4;
#pragma unroll 1
            for (int r = 0; r < nsl; r++) {
                const uint32_t part = sm + (is_main ? OFF_PARTH : OFF_PART + r * 1152);
                gemv32_partial(sm + (is_main ? OFF_W1 : r * SLICE), bar0 + (is_main ? IT_W1 : 4 * r) * 8, sm + OFF_Y, part, warp, lane);
                if (warp < 8) bar_arrive(NB_HPART + r, 288);
                else {
                    bar_sync(NB_HPART + r, 288);
                    const float bv = r == 0 ? bias[0] : r == 1 ? bias[1] : r == 2 ? bias[2] : bias[3];
                    sts_bf(sm + OFF_COEF + ((is_main ? 32 : 32 * r) + lane) * 2, gelu_bias(sum9(part + lane * 4), bv));
                }
            }
            __syncwarp();
            if (!is_main && lane == 0) mbar_arrive(bar0 + BAR_EQ * 8);
            if (warp == 8 && lane == 0) mbar_arrive(bar0 + BAR_H * 8);
        }
        mbar_wait(bar0 + BAR_H * 8);
        float acc[4][4];
#pragma unroll
        for (int j = 0; j < 4; j++) { acc[j][0] = acc[j][1] = acc[j][2] = acc[j][3] = 0.f; }
        const int t = lane & 3;
        const uint32_t rel = warp * 1024 + (lane & 7) * 128 + (((lane >> 3) ^ (lane & 7)) << 4);
        auto load8 = [&](unsigned (&f)[8], uint32_t wa) {
            ldsm4t(reinterpret_cast<unsigned (&)[4]>(f[0]), wa);
            ldsm4t(reinterpret_cast<unsigned (&)[4]>(f[4]), wa ^ 64);
        };
        auto mma8 = [&](const unsigned (&f)[8], unsigned b) {
#pragma unroll
            for (int j = 0; j < 4; j++) mma1688(acc[j], f[2 * j], f[2 * j + 1], b);
        };
        unsigned f[2][8];
        if (is_main) {
            unsigned bc[4];
#pragma unroll
            for (int k = 0; k < 4; k++) bc[k] = lds_u(sm + OFF_COEF + 64 + t * 4 + k * 16);
#pragma unroll
            for (int k = 0; k < 4; k++) {
                mbar_wait(bar0 + (IT_W2 + k) * 8);
                load8(f[k & 1], sm + rel + OFF_B + k * BLK);
                if (k > 0) mma8(f[(k - 1) & 1], bc[k - 1]);
            }
            mma8(f[1], bc[3]);
            mbar_wait(bar0 + BAR_O * 8);
#pragma unroll
            for (int k = 0; k < 4; k++) bc[k] = lds_u(sm + OFF_COEF + t * 4 + k * 16);
            const uint32_t wb = sm + OFF_WO + rel + warp * 3072;
            unsigned g[2][8];
            mbar_wait(bar0 + (IT_WO + (warp / 3 + 2 * cta) % 3) * 8);
            load8(f[0], wb); load8(f[1], wb + 1024); load8(g[0], wb + 2048); load8(g[1], wb + 3072);
#pragma unroll
            for (int j = 0; j < 4; j++) {
                const unsigned a[4] = {f[0][2 * j], f[0][2 * j + 1], f[1][2 * j], f[1][2 * j + 1]};
                mma16816(acc[j], a, bc[0], bc[1]);
            }
#pragma unroll
            for (int j = 0; j < 4; j++) {
                const unsigned a[4] = {g[0][2 * j], g[0][2 * j + 1], g[1][2 * j], g[1][2 * j + 1]};
                mma16816(acc[j], a, bc[2], bc[3]);
            }
        } else {
            uint32_t wa = sm + 4 * SLICE + rel, ca = sm + OFF_COEF + t * 4, bar = bar0 + 16 * 8;
#pragma unroll 1
            for (int b = 0; b < 16; b++) {
                const unsigned bc = lds_u(ca);
                mbar_wait(bar);
                load8(f[0], wa);
                mma8(f[0], bc);
                wa += BLK; ca += 16; bar += 8;
                if (b == 3) wa = sm + rel;
            }
            mbar_wait(bar0 + BAR_Z * 8);
        }
        const float v0 = t == 0 ? acc[0][0] : t == 1 ? acc[1][2] : acc[3][0];
        const float v1 = t == 0 ? acc[0][2] : t == 1 ? acc[2][0] : acc[3][2];
        const float v2 = t == 0 ? acc[1][0] : t == 1 ? acc[2][2] : 0.f;
        if (t < 3) {
            float o0, o1, o2, cnt;
            asm volatile("atom.relaxed.gpu.global.add.v4.f32 {%0,%1,%2,%3}, [%4], {%5,%6,%7,%8};"
                         : "=f"(o0), "=f"(o1), "=f"(o2), "=f"(cnt) : "l"(adst), "f"(v0), "f"(v1), "f"(v2), "f"(1.f) : "memory");
            if (cnt == (float)(NCTA - 1)) {
                odst2[0] = __float2bfloat16_rn(o0 + v0);
                odst2[8] = __float2bfloat16_rn(o1 + v1);
                if (t < 2) odst2[16] = __float2bfloat16_rn(o2 + v2);
            }
        }
    }
}

__device__ float f_q[QD], f_h[FF], f_o[QD];

__global__ void __launch_bounds__(256) fb_proj(const __nv_bfloat16* x, const __nv_bfloat16* wq, const __nv_bfloat16* w1, const __nv_bfloat16* b1) {
    __shared__ float xn[D_MODEL], y[D_MODEL];
    if (threadIdx.x < 32) {
        float v[18];
        for (int i = 0; i < 18; i++) v[i] = __bfloat162float(x[threadIdx.x + 32 * i]);
        layernorm18(v);
        for (int i = 0; i < 18; i++) xn[threadIdx.x + 32 * i] = v[i];
        layernorm18(v);
        for (int i = 0; i < 18; i++) y[threadIdx.x + 32 * i] = v[i];
    }
    __syncthreads();
    const int j = blockIdx.x * 256 + threadIdx.x;
    float a = 0.f;
    if (j < QD) {
        for (int i = 0; i < D_MODEL; i++) a = fmaf(xn[i], __bfloat162float(wq[(size_t)i * QD + j]), a);
        f_q[j] = bf_round(a);
    } else {
        for (int i = 0; i < D_MODEL; i++) a = fmaf(y[i], __bfloat162float(w1[(size_t)i * FF + j - QD]), a);
        f_h[j - QD] = bf_round(gelu_bias(a, __bfloat162float(b1[j - QD])));
    }
}
__global__ void __launch_bounds__(128) fb_attn(const __nv_bfloat16* kc, const __nv_bfloat16* vc) {
    __shared__ float s[WINDOW], red[128];
    const int h = blockIdx.x, t = threadIdx.x;
    const size_t base = ((size_t)(h >> 1) * SK + (SK - WINDOW)) * 128;
    float m = -INFINITY;
    for (int k = t; k < WINDOW; k += 128) {
        float a = 0.f;
        for (int d = 0; d < 128; d++) a = fmaf(f_q[h * 128 + d], __bfloat162float(kc[base + (size_t)k * 128 + d]), a);
        s[k] = bf_round(bf_round(a) * 0.08838834764831845f);
        m = fmaxf(m, s[k]);
    }
    red[t] = m; __syncthreads();
    for (int i = 0; i < 128; i++) m = fmaxf(m, red[i]);
    __syncthreads();
    float l = 0.f;
    for (int k = t; k < WINDOW; k += 128) { s[k] = __expf(s[k] - m); l += s[k]; }
    red[t] = l; __syncthreads();
    l = 0.f;
    for (int i = 0; i < 128; i++) l += red[i];
    float a = 0.f;
    for (int k = 0; k < WINDOW; k++) a = fmaf(s[k], __bfloat162float(vc[base + (size_t)k * 128 + t]), a);
    f_o[h * 128 + t] = bf_round(a / l);
}
__global__ void __launch_bounds__(64) fb_out(const __nv_bfloat16* x, const __nv_bfloat16* wo, const __nv_bfloat16* w2, const __nv_bfloat16* b2, __nv_bfloat16* out) {
    const int j = blockIdx.x * 64 + threadIdx.x;
    float a = __bfloat162float(x[j]) + __bfloat162float(b2[j]);
    for (int i = 0; i < QD; i++) a = fmaf(f_o[i], __bfloat162float(wo[(size_t)i * D_MODEL + j]), a);
    for (int i = 0; i < FF; i++) a = fmaf(f_h[i], __bfloat162float(w2[(size_t)i * D_MODEL + j]), a);
    out[j] = __float2bfloat16_rn(a);
}

typedef CUresult (*EncodeTiledFn)(CUtensorMap*, CUtensorMapDataType, cuuint32_t, void*, const cuuint64_t*, const cuuint64_t*,
                                  const cuuint32_t*, const cuuint32_t*, CUtensorMapInterleave, CUtensorMapSwizzle,
                                  CUtensorMapL2promotion, CUtensorMapFloatOOBfill);

}

extern "C" void kernel_launch(void* const* d_in, const int* in_sizes, int n_in, void* d_out, int out_size) {
    (void)in_sizes; (void)n_in; (void)out_size;
    typedef const __nv_bfloat16* bfp;
    static EncodeTiledFn encode = nullptr;
    static int mode = -1;
    if (mode < 0) {
        void* fn = nullptr;
        cudaDriverEntryPointQueryResult qr;
        cudaGetDriverEntryPoint("cuTensorMapEncodeTiled", &fn, cudaEnableDefault, &qr);
        encode = (EncodeTiledFn)fn;
        int dev = 0, sms = 0, per_sm = 0;
        cudaGetDevice(&dev);
        cudaDeviceGetAttribute(&sms, cudaDevAttrMultiProcessorCount, dev);
        cudaFuncSetAttribute(fused_decode_kernel, cudaFuncAttributeMaxDynamicSharedMemorySize, SMEM_BYTES);
        cudaOccupancyMaxActiveBlocksPerMultiprocessor(&per_sm, fused_decode_kernel, NTHREADS, SMEM_BYTES);
        mode = (encode != nullptr && sms * per_sm >= NCTA) ? 1 : 0;
    }
    if (mode == 0) {
        fb_proj<<<(QD + FF) / 256, 256>>>((bfp)d_in[0], (bfp)d_in[3], (bfp)d_in[6], (bfp)d_in[7]);
        fb_attn<<<32, 128>>>((bfp)d_in[1], (bfp)d_in[2]);
        fb_out<<<D_MODEL / 64, 64>>>((bfp)d_in[0], (bfp)d_in[4], (bfp)d_in[8], (bfp)d_in[9], (__nv_bfloat16*)d_out);
        return;
    }
    CUtensorMap mq, m1, mk, mv, mo, m2;
    const cuuint32_t es[3] = {1, 1, 1};
    auto enc_map = [&](CUtensorMap* m, cuuint32_t rank, void* ptr, const cuuint64_t* dims, const cuuint64_t* strides,
                       const cuuint32_t* box, CUtensorMapSwizzle sw) {
        encode(m, CU_TENSOR_MAP_DATA_TYPE_BFLOAT16, rank, ptr, dims, strides, box, es, CU_TENSOR_MAP_INTERLEAVE_NONE, sw,
               CU_TENSOR_MAP_L2_PROMOTION_L2_128B, CU_TENSOR_MAP_FLOAT_OOB_FILL_NONE);
    };
    {
        const cuuint64_t dq[2] = {QD, D_MODEL}, sq[1] = {QD * 2}, d1[2] = {FF, D_MODEL}, s1[1] = {FF * 2};
        const cuuint32_t bx[2] = {32, 144};
        enc_map(&mq, 2, d_in[3], dq, sq, bx, CU_TENSOR_MAP_SWIZZLE_64B);
        enc_map(&m1, 2, d_in[6], d1, s1, bx, CU_TENSOR_MAP_SWIZZLE_64B);
    }
    {
        const cuuint64_t d[3] = {64, (cuuint64_t)16 * SK, 2}, st[2] = {256, 128};
        const cuuint32_t bx[3] = {64, 32, 2};
        enc_map(&mk, 3, d_in[1], d, st, bx, CU_TENSOR_MAP_SWIZZLE_128B);
        enc_map(&mv, 3, d_in[2], d, st, bx, CU_TENSOR_MAP_SWIZZLE_128B);
    }
    {
        const cuuint64_t dO[3] = {64, QD, 9}, d2[3] = {64, FF, 9}, st[2] = {D_MODEL * 2, 128};
        const cuuint32_t bx[3] = {64, 8, 9}, bxo[3] = {64, 32, 3};
        enc_map(&mo, 3, d_in[4], dO, st, bxo, CU_TENSOR_MAP_SWIZZLE_128B);
        enc_map(&m2, 3, d_in[8], d2, st, bx, CU_TENSOR_MAP_SWIZZLE_128B);
    }
    fused_decode_kernel<<<NCTA, NTHREADS, SMEM_BYTES>>>(
        mq, m1, mk, mv, mo, m2, (bfp)d_in[0], (bfp)d_in[7], (bfp)d_in[9], (__nv_bfloat16*)d_out);
}
```
